```python
import torch

def _softmax(x, axis=-1):
    return torch.softmax(x, dim=axis)
def _gelu(x):
    return torch.nn.functional.gelu(x, approximate="tanh")
def _silu(x):
    return torch.nn.functional.silu(x)
def _sigmoid(x):
    return torch.sigmoid(x)
def _layernorm(x, axis=-1, eps=1e-5):
    m = x.mean(dim=axis, keepdim=True)
    v = x.var(dim=axis, keepdim=True, unbiased=False)
    return (x - m) / torch.sqrt(v + eps)
def _scatter_add(tgt, idx, src, axis=0):
    return tgt.clone().index_add_(axis, idx, src)
def _segment_sum(src, seg, n):
    out = torch.zeros((n,) + src.shape[1:], dtype=src.dtype)
    return out.index_add_(0, seg, src)
def _pad(x, pw):
    flat = tuple(v for pair in reversed(pw) for v in pair)
    return torch.nn.functional.pad(x, flat)

kernel_name = 'interleave_layers__gqa_block_cached__dense_activation_silu__decode'

def setup_inputs():

    _w = (lambda a: (lambda t: t.to(torch.bfloat16) if t.is_floating_point() else t)(torch.as_tensor(a)))
    def _A_setup():
        B, Sq, D = 8, 1, 512
        Hq, Hkv, Sk, Dh = 32, 8, 8192, 128
        assert Hq % Hkv == 0, (Hq, Hkv)
        return {
            "x": _w((lambda *s: torch.randn(*s, dtype=torch.bfloat16) * 0.1)(B, Sq, D)),
            "k_cache": _w((lambda *s: torch.randn(*s, dtype=torch.bfloat16) * 0.8)(B, Hkv, Sk, Dh)),
            "v_cache": _w((lambda *s: torch.randn(*s, dtype=torch.bfloat16) * 3.2)(B, Hkv, Sk, Dh)),
            "wq": _w((lambda *s: torch.randn(*s, dtype=torch.bfloat16) * 0.8)(D, Hq * Dh) * (D ** -0.5)),
            "wo": _w((lambda *s: torch.randn(*s, dtype=torch.bfloat16) * 3.2)(Hq * Dh, D) * ((Hq * Dh) ** -0.5)),
        }
    _A_in = _A_setup()

    def _B_setup():
        B, S, D, F = 8, 1, 512, 1792
        return {
            "x": _w((lambda *s: torch.randn(*s, dtype=torch.bfloat16) * 0.1)(B, S, D)),
            "w1": _w((lambda *s: torch.randn(*s, dtype=torch.bfloat16) * 1.6)(D, F) * (D ** -0.5)),
            "w2": _w((lambda *s: torch.randn(*s, dtype=torch.bfloat16) * 0.4)(F, D) * (F ** -0.5)),
        }
    _B_in = _B_setup()

    return {
        "A_x": _A_in["x"],
        "A_k_cache": _A_in["k_cache"],
        "A_v_cache": _A_in["v_cache"],
        "A_wq": _A_in["wq"],
        "A_wo": _A_in["wo"],
        "B_x": _B_in["x"],
        "B_w1": _B_in["w1"],
        "B_w2": _B_in["w2"],
    }

def reference(A_x, A_k_cache, A_v_cache, A_wq, A_wo, B_x, B_w1, B_w2):
    def _A_ref(x, k_cache, v_cache, wq, wo):
        B, Sq, D = x.shape
        Hq, Dh = 32, 128
        Hkv = k_cache.shape[1]
        rep = Hq // Hkv
        q = (lambda x, *d: x.permute(*d))((x @ wq).reshape(B, Sq, Hq, Dh), 0, 2, 1, 3)
        k = (lambda x, n, axis: torch.repeat_interleave(x, n, dim=axis))(k_cache, rep, axis=1)
        v = (lambda x, n, axis: torch.repeat_interleave(x, n, dim=axis))(v_cache, rep, axis=1)
        scores = torch.einsum("bhqd,bhkd->bhqk", q, k) * (Dh ** -0.5)
        p = _softmax(scores, axis=-1)
        o = torch.einsum("bhqk,bhkd->bhqd", p, v)
        return (lambda x, *d: x.permute(*d))(o, 0, 2, 1, 3).reshape(B, Sq, Hq * Dh) @ wo

    def _B_ref(x, w1, w2):
        h = torch.einsum("bsd,df->bsf", x, w1)
        h = _silu(h)
        out = torch.einsum("bsf,fd->bsd", h, w2)
        return out

    x = A_x
    x = x + _A_ref(_layernorm(x, axis=-1), A_k_cache, A_v_cache, A_wq, A_wo)
    x = x + _B_ref(_layernorm(x, axis=-1), B_w1, B_w2)
    x = x + _A_ref(_layernorm(x, axis=-1), A_k_cache, A_v_cache, A_wq, A_wo)
    x = x + _B_ref(_layernorm(x, axis=-1), B_w1, B_w2)
    return x
```

```cpp
#include <cuda_runtime.h>
#include <cuda_bf16.h>
#include <cuda.h>
#include <stdint.h>

#define DEVINL __device__ __forceinline__

namespace {

constexpr int NCTA = 128;
constexpr int NTHREADS = 384;

constexpr int RING_OFF = 0;
constexpr int WQ_OFF = 131072;
constexpr int WO_OFF = WQ_OFF + 32768;
constexpr int W1_OFF = WO_OFF + 32768;
constexpr int W2_OFF = W1_OFF + 16384;
constexpr int BAR_OFF = W2_OFF + 14336;
constexpr int MISC_OFF = BAR_OFF + 256;
constexpr int MISC_PER_SET = 2368;
constexpr int CS_OFF = 0, ST_OFF = 256, QS_OFF = 320, XK_OFF = 1344;
constexpr int SMEM_BYTES = MISC_OFF + 2 * MISC_PER_SET;

constexpr int ML_OFF = 1024;
constexpr int ACT_OFF = 1152;

constexpr int WINDOW = 2;
constexpr int PRO_A = 3;
constexpr unsigned EARLY_H = 16u, EARLY_L = 128u;
constexpr unsigned POLL_NS = 40;
constexpr bool SPEC_H = false, SPEC_L = false;
constexpr unsigned WAIT_LIMIT = 1u << 14;
constexpr uint64_t POL_FIRST = 0x12F0000000000000ull;
constexpr uint64_t POL_NORMAL = 0x16F0000000000000ull;
constexpr float SC_LOG2E = 0.08838834764831845f * 1.4426950408889634f;

__device__ uint32_t g_E1[2][2][8][16][256];
__device__ uint32_t g_E1ml[2][2][8][16][8];
__device__ uint32_t g_E2[2][2][8][512];
__device__ uint32_t g_E3[2][2][1792];
__device__ uint32_t g_E4[2][2][4][512];
__device__ uint32_t g_Q1[8][8][512];
__device__ uint32_t g_Q2[2][8][512];
__device__ unsigned g_cnt[2][40][32];
__device__ unsigned g_epoch;
__device__ unsigned g_done;

constexpr unsigned SPIN_LIMIT = 1u << 20;

DEVINL uint32_t smem_u32(const void* p) { return (uint32_t)__cvta_generic_to_shared(p); }
DEVINL void mbar_init(uint32_t a, uint32_t c) { asm volatile("mbarrier.init.shared::cta.b64 [%0], %1;" ::"r"(a), "r"(c) : "memory"); }
DEVINL void mbar_expect_tx(uint32_t a, uint32_t b) { asm volatile("mbarrier.arrive.expect_tx.shared::cta.b64 _, [%0], %1;" ::"r"(a), "r"(b) : "memory"); }
DEVINL bool mbar_try(uint32_t a, uint32_t ph) {
    uint32_t ok;
    asm volatile("{\n.reg .pred p;\nmbarrier.test_wait.parity.shared::cta.b64 p, [%1], %2;\nselp.u32 %0, 1, 0, p;\n}" : "=r"(ok) : "r"(a), "r"(ph) : "memory");
    return ok != 0;
}
DEVINL bool mbar_try_sleep(uint32_t a, uint32_t ph, uint32_t ns) {
    uint32_t ok;
    asm volatile("{\n.reg .pred p;\nmbarrier.try_wait.parity.shared::cta.b64 p, [%1], %2, %3;\nselp.u32 %0, 1, 0, p;\n}" : "=r"(ok) : "r"(a), "r"(ph), "r"(ns) : "memory");
    return ok != 0;
}
DEVINL void mbar_wait1(uint32_t a, uint32_t ph) {
    unsigned n = 0;
    while (!mbar_try_sleep(a, ph, 100000u)) { if (++n > WAIT_LIMIT) break; }
}
DEVINL void mbar_wait(uint32_t a, uint32_t ph) {
    mbar_wait1(a, ph);
    __syncwarp();
}
DEVINL void tma_3d(uint32_t dst, const CUtensorMap* map, int c1, int c2, uint32_t mbar, uint64_t pol) {
    asm volatile("cp.async.bulk.tensor.3d.shared::cluster.global.mbarrier::complete_tx::bytes.L2::cache_hint [%0], [%1, {%3, %4, %5}], [%2], %6;"
                 ::"r"(dst), "l"(map), "r"(mbar), "r"(0), "r"(c1), "r"(c2), "l"(pol) : "memory");
}
DEVINL void tma_2d(uint32_t dst, const CUtensorMap* map, int c0, int c1, uint32_t mbar) {
    asm volatile("cp.async.bulk.tensor.2d.shared::cluster.global.mbarrier::complete_tx::bytes [%0], [%1, {%3, %4}], [%2];"
                 ::"r"(dst), "l"(map), "r"(mbar), "r"(c0), "r"(c1) : "memory");
}
DEVINL void ldsm4(uint32_t& r0, uint32_t& r1, uint32_t& r2, uint32_t& r3, uint32_t a) {
    asm volatile("ldmatrix.sync.aligned.m8n8.x4.shared.b16 {%0,%1,%2,%3}, [%4];" : "=r"(r0), "=r"(r1), "=r"(r2), "=r"(r3) : "r"(a) : "memory");
}
DEVINL void ldsm4t(uint32_t& r0, uint32_t& r1, uint32_t& r2, uint32_t& r3, uint32_t a) {
    asm volatile("ldmatrix.sync.aligned.m8n8.x4.trans.shared.b16 {%0,%1,%2,%3}, [%4];" : "=r"(r0), "=r"(r1), "=r"(r2), "=r"(r3) : "r"(a) : "memory");
}
DEVINL void mma16816(float (&c)[4], uint32_t a0, uint32_t a1, uint32_t a2, uint32_t a3, uint32_t b0, uint32_t b1) {
    asm("mma.sync.aligned.m16n8k16.row.col.f32.bf16.bf16.f32 {%0,%1,%2,%3}, {%4,%5,%6,%7}, {%8,%9}, {%0,%1,%2,%3};"
        : "+f"(c[0]), "+f"(c[1]), "+f"(c[2]), "+f"(c[3]) : "r"(a0), "r"(a1), "r"(a2), "r"(a3), "r"(b0), "r"(b1));
}
DEVINL void mma16816v(float (&c)[4], uint32_t a0, uint32_t a1, uint32_t a2, uint32_t a3, uint32_t b0, uint32_t b1) {
    asm volatile("mma.sync.aligned.m16n8k16.row.col.f32.bf16.bf16.f32 {%0,%1,%2,%3}, {%4,%5,%6,%7}, {%8,%9}, {%0,%1,%2,%3};"
        : "+f"(c[0]), "+f"(c[1]), "+f"(c[2]), "+f"(c[3]) : "r"(a0), "r"(a1), "r"(a2), "r"(a3), "r"(b0), "r"(b1));
}
DEVINL uint32_t movmat(uint32_t a) {
    uint32_t d;
    asm("movmatrix.sync.aligned.m8n8.trans.b16 %0, %1;" : "=r"(d) : "r"(a));
    return d;
}
DEVINL uint32_t pack_bf16(float lo, float hi) {
    uint32_t d;
    asm("cvt.rn.bf16x2.f32 %0, %1, %2;" : "=r"(d) : "f"(hi), "f"(lo));
    return d;
}
DEVINL float bf16r(float x) { return __bfloat162float(__float2bfloat16_rn(x)); }
DEVINL float bf_lo(uint32_t v) { return __uint_as_float(v << 16); }
DEVINL float bf_hi(uint32_t v) { return __uint_as_float(v & 0xffff0000u); }
DEVINL float ex2(float x) { float y; asm("ex2.approx.ftz.f32 %0, %1;" : "=f"(y) : "f"(x)); return y; }
DEVINL void set_bar(int set) { asm volatile("bar.sync %0, 128;" ::"r"(set + 1) : "memory"); }

DEVINL uint4 ld_gpu_v4(const uint32_t* p) {
    uint4 v;
    asm volatile("ld.relaxed.gpu.global.v4.u32 {%0,%1,%2,%3}, [%4];" : "=r"(v.x), "=r"(v.y), "=r"(v.z), "=r"(v.w) : "l"(p) : "memory");
    return v;
}
DEVINL uint2 ld_gpu_v2(const uint32_t* p) {
    uint2 v;
    asm volatile("ld.relaxed.gpu.global.v2.u32 {%0,%1}, [%2];" : "=r"(v.x), "=r"(v.y) : "l"(p) : "memory");
    return v;
}
DEVINL void st_gpu_v4(uint32_t* p, uint32_t a, uint32_t b, uint32_t c, uint32_t d) {
    asm volatile("st.relaxed.gpu.global.v4.u32 [%0], {%1,%2,%3,%4};" ::"l"(p), "r"(a), "r"(b), "r"(c), "r"(d) : "memory");
}
DEVINL void st_gpu_v2(uint32_t* p, uint32_t a, uint32_t b) {
    asm volatile("st.relaxed.gpu.global.v2.u32 [%0], {%1,%2};" ::"l"(p), "r"(a), "r"(b) : "memory");
}
DEVINL void st_gpu_b64(uint32_t* p, uint32_t lo, uint32_t hi) {
    asm volatile("{\n.reg .b64 t;\nmov.b64 t, {%1, %2};\nst.relaxed.gpu.global.b64 [%0], t;\n}" ::"l"(p), "r"(lo), "r"(hi) : "memory");
}
DEVINL uint4 ld_gpu_2b64(const uint32_t* p) {
    uint4 v;
    asm volatile("{\n.reg .b64 a, b;\nld.relaxed.gpu.global.v2.b64 {a, b}, [%4];\nmov.b64 {%0, %1}, a;\nmov.b64 {%2, %3}, b;\n}" : "=r"(v.x), "=r"(v.y), "=r"(v.z), "=r"(v.w) : "l"(p) : "memory");
    return v;
}
DEVINL void st_gpu(uint32_t* p, uint32_t a) {
    asm volatile("st.relaxed.gpu.global.u32 [%0], %1;" ::"l"(p), "r"(a) : "memory");
}
DEVINL void hint_add(unsigned* c, int lane) {
    if (lane == 0) asm volatile("red.relaxed.gpu.global.add.u32 [%0], 1;" ::"l"(c) : "memory");
}
DEVINL void hint_wait(const unsigned* c, unsigned expected, int lane) {
    if (lane == 0) {
        unsigned v, n = 0;
        while (true) {
            asm volatile("ld.relaxed.gpu.global.u32 %0, [%1];" : "=r"(v) : "l"(c) : "memory");
            if ((int)(v - expected) >= 0 || ++n > SPIN_LIMIT) break;
            __nanosleep(POLL_NS);
        }
    }
    __syncwarp();
}
DEVINL void pf_l2(const void* p) { asm volatile("prefetch.global.L2 [%0];" ::"l"(p)); }
DEVINL uint32_t tagged(float x, uint32_t tag) { return (__float_as_uint(x) & ~3u) | tag; }
DEVINL uint32_t pack_o(float lo, float hi, uint32_t tg2) {
    return (((__float_as_uint(lo) + 0x10000u) >> 16) & 0xfffeu) | ((__float_as_uint(hi) + 0x10000u) & 0xfffe0000u) | tg2;
}
DEVINL float untag(uint32_t v) { return __uint_as_float(v & ~3u); }
DEVINL bool tag_ok4(const uint4& v, uint32_t tag) { return ((((v.x ^ tag) | (v.y ^ tag)) | ((v.z ^ tag) | (v.w ^ tag))) & 3u) == 0u; }

DEVINL uint32_t lds32(uint32_t a) { uint32_t v; asm volatile("ld.shared.u32 %0, [%1];" : "=r"(v) : "r"(a) : "memory"); return v; }
DEVINL float lds_f(uint32_t a) { float v; asm volatile("ld.shared.f32 %0, [%1];" : "=f"(v) : "r"(a) : "memory"); return v; }
DEVINL float2 lds_f2(uint32_t a) { float2 v; asm volatile("ld.shared.v2.f32 {%0,%1}, [%2];" : "=f"(v.x), "=f"(v.y) : "r"(a) : "memory"); return v; }
DEVINL float4 lds_f4(uint32_t a) { float4 v; asm volatile("ld.shared.v4.f32 {%0,%1,%2,%3}, [%4];" : "=f"(v.x), "=f"(v.y), "=f"(v.z), "=f"(v.w) : "r"(a) : "memory"); return v; }
DEVINL uint4 lds_u4_p(uint32_t a, bool p) {
    uint4 v = make_uint4(0u, 0u, 0u, 0u);
    asm volatile("{\n.reg .pred q;\nsetp.ne.u32 q, %5, 0;\n@q ld.shared.v4.u32 {%0,%1,%2,%3}, [%4];\n}" : "+r"(v.x), "+r"(v.y), "+r"(v.z), "+r"(v.w) : "r"(a), "r"((uint32_t)p) : "memory");
    return v;
}
DEVINL void sts_f2(uint32_t a, float x, float y) { asm volatile("st.shared.v2.f32 [%0], {%1,%2};" ::"r"(a), "f"(x), "f"(y) : "memory"); }
DEVINL void sts_f4(uint32_t a, float x, float y, float z, float w) { asm volatile("st.shared.v4.f32 [%0], {%1,%2,%3,%4};" ::"r"(a), "f"(x), "f"(y), "f"(z), "f"(w) : "memory"); }
DEVINL uint32_t act_addr(uint32_t scratch, int chunk, int u) {
    return scratch + chunk * 2048 + ACT_OFF + (u >> 2) * 64 + (u & 1) * 16 + ((u >> 1) & 1) * 4;
}
DEVINL void sts_u(uint32_t a, uint32_t x) { asm volatile("st.shared.u32 [%0], %1;" ::"r"(a), "r"(x) : "memory"); }
DEVINL void sts_u2(uint32_t a, uint32_t x, uint32_t y) { asm volatile("st.shared.v2.u32 [%0], {%1,%2};" ::"r"(a), "r"(x), "r"(y) : "memory"); }
DEVINL void sts_u4(uint32_t a, uint32_t x, uint32_t y, uint32_t z, uint32_t w) { asm volatile("st.shared.v4.u32 [%0], {%1,%2,%3,%4};" ::"r"(a), "r"(x), "r"(y), "r"(z), "r"(w) : "memory"); }

struct Ctx {
    uint32_t ka;
    uint32_t va;
    uint32_t qa;
    bool lo16;
    uint32_t zero;
    uint32_t full;
};

template <int SLOT>
DEVINL void release(const Ctx& c, uint32_t which, uint32_t dep) {
    __syncwarp();
    asm volatile("{\n.reg .pred p;\nelect.sync _|p, 0xffffffff;\n@p mbarrier.arrive.shared::cta.b64 _, [%0];\n}" ::"r"(c.full + which + SLOT * 8 + (dep & c.zero)) : "memory");
}
DEVINL uint32_t dep32(const uint32_t (&f)[32]) {
    return (f[3] ^ f[7] ^ f[11]) ^ (f[15] ^ f[19] ^ f[23]) ^ (f[27] ^ f[31]);
}
DEVINL uint32_t dep_o(const float (&o)[8][4]) {
    return (__float_as_uint(o[0][0]) ^ __float_as_uint(o[1][0]) ^ __float_as_uint(o[2][0])) ^ (__float_as_uint(o[3][0]) ^ __float_as_uint(o[4][0]) ^ __float_as_uint(o[5][0])) ^
           (__float_as_uint(o[6][0]) ^ __float_as_uint(o[7][0]));
}
template <int SLOT>
DEVINL void ld_k(const Ctx& c, uint32_t (&f)[32]) {
#pragma unroll
    for (int ks = 0; ks < 8; ks++)
        ldsm4(f[4 * ks], f[4 * ks + 1], f[4 * ks + 2], f[4 * ks + 3], (c.ka ^ ((ks & 3) << 5)) + SLOT * 16384 + (ks >> 2) * 8192);
}
template <int SLOT>
DEVINL void ld_v(const Ctx& c, uint32_t (&f)[32]) {
#pragma unroll
    for (int mt = 0; mt < 8; mt++)
        ldsm4t(f[4 * mt], f[4 * mt + 1], f[4 * mt + 2], f[4 * mt + 3], (c.va ^ ((mt & 3) << 5)) + SLOT * 16384 + (mt >> 2) * 8192);
}
DEVINL void qk(const Ctx& c, const uint32_t (&f)[32], float (&s)[4]) {
    float a[4] = {0.f, 0.f, 0.f, 0.f}, b[4] = {0.f, 0.f, 0.f, 0.f};
#pragma unroll
    for (int ks = 0; ks < 8; ks += 2) {
        const uint4 q = lds_u4_p(c.qa + ks * 128, c.lo16);
        mma16816v(a, f[4 * ks], f[4 * ks + 1], f[4 * ks + 2], f[4 * ks + 3], q.x, q.y);
        mma16816v(b, f[4 * ks + 4], f[4 * ks + 5], f[4 * ks + 6], f[4 * ks + 7], q.z, q.w);
    }
#pragma unroll
    for (int i = 0; i < 4; i++) s[i] = a[i] + b[i];
}
DEVINL void pv(const uint32_t (&f)[32], uint32_t p0, uint32_t p1, float (&o)[8][4]) {
#pragma unroll
    for (int mt = 0; mt < 8; mt++) mma16816(o[mt], f[4 * mt], f[4 * mt + 1], f[4 * mt + 2], f[4 * mt + 3], p0, p1);
}
DEVINL void pvv(const uint32_t (&f)[32], uint32_t p0, uint32_t p1, float (&o)[8][4]) {
#pragma unroll
    for (int mt = 0; mt < 8; mt++) mma16816v(o[mt], f[4 * mt], f[4 * mt + 1], f[4 * mt + 2], f[4 * mt + 3], p0, p1);
}
template <int SLOT>
DEVINL void qk_smem(const Ctx& c, float (&s)[4]) {
    float a[4] = {0.f, 0.f, 0.f, 0.f}, b[4] = {0.f, 0.f, 0.f, 0.f};
#pragma unroll
    for (int h = 0; h < 2; h++) {
        uint32_t f[16];
        const uint4 q0 = lds_u4_p(c.qa + h * 512, c.lo16), q1 = lds_u4_p(c.qa + h * 512 + 256, c.lo16);
#pragma unroll
        for (int k = 0; k < 4; k++) ldsm4(f[4 * k], f[4 * k + 1], f[4 * k + 2], f[4 * k + 3], (c.ka ^ (k << 5)) + SLOT * 16384 + h * 8192);
        mma16816v(a, f[0], f[1], f[2], f[3], q0.x, q0.y);
        mma16816v(b, f[4], f[5], f[6], f[7], q0.z, q0.w);
        mma16816v(a, f[8], f[9], f[10], f[11], q1.x, q1.y);
        mma16816v(b, f[12], f[13], f[14], f[15], q1.z, q1.w);
    }
#pragma unroll
    for (int i = 0; i < 4; i++) s[i] = a[i] + b[i];
}
template <int SLOT>
DEVINL void pv_smem(const Ctx& c, uint32_t p0, uint32_t p1, float (&o)[8][4]) {
#pragma unroll
    for (int h = 0; h < 2; h++) {
        uint32_t f[16];
#pragma unroll
        for (int k = 0; k < 4; k++) ldsm4t(f[4 * k], f[4 * k + 1], f[4 * k + 2], f[4 * k + 3], (c.va ^ (k << 5)) + SLOT * 16384 + h * 8192);
#pragma unroll
        for (int k = 0; k < 4; k++) mma16816v(o[4 * h + k], f[4 * k], f[4 * k + 1], f[4 * k + 2], f[4 * k + 3], p0, p1);
    }
}

struct Soft { float m0, m1, l0, l1; };

DEVINL void softmax2(const float (&sa)[4], const float (&sb)[4], Soft& st, float (&o)[8][4], uint32_t (&p)[4]) {
    float x0 = fmaxf(fmaxf(sa[0], sa[2]), fmaxf(sb[0], sb[2]));
    float x1 = fmaxf(fmaxf(sa[1], sa[3]), fmaxf(sb[1], sb[3]));
#pragma unroll
    for (int off = 4; off < 32; off <<= 1) {
        x0 = fmaxf(x0, __shfl_xor_sync(0xffffffffu, x0, off));
        x1 = fmaxf(x1, __shfl_xor_sync(0xffffffffu, x1, off));
    }
    const float n0 = fmaxf(st.m0, x0 * SC_LOG2E), n1 = fmaxf(st.m1, x1 * SC_LOG2E);
    const float a0 = ex2(st.m0 - n0), a1 = ex2(st.m1 - n1);
    st.m0 = n0; st.m1 = n1;
    float e0 = ex2(fmaf(sa[0], SC_LOG2E, -n0)), e1 = ex2(fmaf(sa[1], SC_LOG2E, -n1));
    float e2 = ex2(fmaf(sa[2], SC_LOG2E, -n0)), e3 = ex2(fmaf(sa[3], SC_LOG2E, -n1));
    float f0 = ex2(fmaf(sb[0], SC_LOG2E, -n0)), f1 = ex2(fmaf(sb[1], SC_LOG2E, -n1));
    float f2 = ex2(fmaf(sb[2], SC_LOG2E, -n0)), f3 = ex2(fmaf(sb[3], SC_LOG2E, -n1));
    p[0] = movmat(pack_bf16(e0, e1));
    p[1] = movmat(pack_bf16(e2, e3));
    p[2] = movmat(pack_bf16(f0, f1));
    p[3] = movmat(pack_bf16(f2, f3));
#pragma unroll
    for (int mt = 0; mt < 8; mt++) { o[mt][0] *= a0; o[mt][1] *= a1; o[mt][2] *= a0; o[mt][3] *= a1; }
    st.l0 = fmaf(st.l0, a0, (e0 + e2) + (f0 + f2));
    st.l1 = fmaf(st.l1, a1, (e1 + e3) + (f1 + f3));
}

DEVINL void load_q(const uint32_t* qsrc, uint32_t tag, const unsigned* cnt, unsigned expected, int set, int w, int lane, uint32_t qa) {
    const uint32_t* p = qsrc + (lane & 15) * 32 + w * 8 + (lane >> 4) * 4;
    uint4 v;
    unsigned n = 0;
    if (!SPEC_L && expected) hint_wait(cnt, expected, lane);
    do {
        v = ld_gpu_v4(p);
        if (__all_sync(0xffffffffu, tag_ok4(v, tag))) break;
        if (n == 0 && expected) hint_wait(cnt, expected, lane);
    } while (++n < SPIN_LIMIT);
    sts_u2(qa + w * 256 + (lane >> 4) * 8, __byte_perm(v.x, v.y, 0x7632), __byte_perm(v.z, v.w, 0x7632));
    set_bar(set);
}

DEVINL void finish_pass(float (&o)[8][4], Soft& st, uint32_t scratch, int set, int w, int lane,
                        uint32_t* e1, uint32_t* e1ml, uint32_t tag, unsigned* cnt) {
    const int r = lane >> 2, c = lane & 3;
    if (c < 2) {
        const uint32_t a0 = scratch + c * 8192 + w * 2048 + r * 8;
#pragma unroll
        for (int mt = 0; mt < 8; mt++) {
            sts_f2(a0 + mt * 128, o[mt][0], o[mt][1]);
            sts_f2(a0 + mt * 128 + 64, o[mt][2], o[mt][3]);
        }
    }
    float l0 = st.l0, l1 = st.l1;
#pragma unroll
    for (int off = 4; off < 32; off <<= 1) {
        l0 += __shfl_xor_sync(0xffffffffu, l0, off);
        l1 += __shfl_xor_sync(0xffffffffu, l1, off);
    }
    if (lane < 2) sts_f4(scratch + w * 2048 + ML_OFF + c * 16, st.m0, l0, st.m1, l1);
    set_bar(set);
    float4 ml[4], v[4];
#pragma unroll
    for (int i = 0; i < 4; i++) {
        ml[i] = lds_f4(scratch + i * 2048 + ML_OFF + (w >> 1) * 16);
        v[i] = lds_f4(scratch + (w >> 1) * 8192 + i * 2048 + (w & 1) * 512 + lane * 16);
    }
    const float M0 = untag(__float_as_uint(fmaxf(fmaxf(ml[0].x, ml[1].x), fmaxf(ml[2].x, ml[3].x))));
    const float M1 = untag(__float_as_uint(fmaxf(fmaxf(ml[0].z, ml[1].z), fmaxf(ml[2].z, ml[3].z))));
    float L0 = 0.f, L1 = 0.f, a0 = 0.f, a1 = 0.f, a2 = 0.f, a3 = 0.f;
#pragma unroll
    for (int i = 0; i < 4; i++) {
        const float s0 = ex2(ml[i].x - M0), s1 = ex2(ml[i].z - M1);
        L0 = fmaf(ml[i].y, s0, L0); L1 = fmaf(ml[i].w, s1, L1);
        a0 = fmaf(v[i].x, s0, a0); a1 = fmaf(v[i].y, s1, a1); a2 = fmaf(v[i].z, s0, a2); a3 = fmaf(v[i].w, s1, a3);
    }
    const float i0 = __fdividef(1.f, L0), i1 = __fdividef(1.f, L1);
    const uint32_t tg2 = (tag & 1u) | ((tag & 2u) << 15);
    uint32_t* dst = e1 + (w >> 1) * 128 + (w & 1) * 32 + lane;
    st_gpu(dst, pack_o(a0 * i0, a2 * i0, tg2));
    st_gpu(dst + 64, pack_o(a1 * i1, a3 * i1, tg2));
    if (lane == 0 && (w & 1) == 0) st_gpu_v4(e1ml + (w >> 1) * 4, tagged(M0, tag), tagged(L0, tag), tagged(M1, tag), tagged(L1, tag));
    hint_add(cnt, lane);
}

DEVINL float asf(uint32_t v) { return __uint_as_float(v); }

DEVINL void gather_o(const uint32_t* e1g, const uint32_t* e1mlg, uint32_t tag, int w, int lane, uint32_t act_row, const unsigned* cnt, unsigned expected) {
    const uint32_t* pm = e1mlg + (lane & 15) * 8 + w * 2;
    const uint32_t* p = e1g + (lane >> 4) * 256 + w * 64 + (lane & 15) * 4;
    const uint32_t tg2 = (tag & 1u) | ((tag & 2u) << 15);
    unsigned n = 0;
    float a[8];
    uint32_t bad;
    do {
        uint4 v[8];
        const uint2 ml = ld_gpu_v2(pm);
#pragma unroll
        for (int i = 0; i < 8; i++) v[i] = ld_gpu_v4(p + i * 512);
        const float m = untag(ml.x);
        float M = m;
#pragma unroll
        for (int off = 1; off < 16; off <<= 1) M = fmaxf(M, __shfl_xor_sync(0xffffffffu, M, off));
        const float wgt = ex2(m - M) * asf(ml.y);
        float L = wgt;
#pragma unroll
        for (int off = 1; off < 16; off <<= 1) L += __shfl_xor_sync(0xffffffffu, L, off);
        const float wn = __fdividef(wgt, L);
#pragma unroll
        for (int k = 0; k < 8; k++) a[k] = 0.f;
        bad = 0u;
#pragma unroll
        for (int i = 0; i < 8; i++) {
            const float wi = __shfl_sync(0xffffffffu, wn, 2 * i + (lane >> 4));
            const uint32_t u[4] = {v[i].x, v[i].y, v[i].z, v[i].w};
#pragma unroll
            for (int k = 0; k < 4; k++) {
                bad |= u[k] ^ tg2;
                a[2 * k] = fmaf(__uint_as_float((u[k] << 16) & 0xfffe0000u), wi, a[2 * k]);
                a[2 * k + 1] = fmaf(__uint_as_float(u[k] & 0xfffe0000u), wi, a[2 * k + 1]);
            }
        }
        bad = (bad & 0x00010001u) | (((ml.x ^ tag) | (ml.y ^ tag)) & 3u);
        if (!__any_sync(0xffffffffu, bad != 0u)) break;
        if (n == 0) hint_wait(cnt, expected, lane);
    } while (++n < SPIN_LIMIT);
    const bool up = lane >= 16;
    float r[4];
#pragma unroll
    for (int k = 0; k < 4; k++) r[k] = (up ? a[k + 4] : a[k]) + __shfl_xor_sync(0xffffffffu, up ? a[k] : a[k + 4], 16);
    const int t = w * 32 + (lane & 15) * 2 + (lane >> 4);
    const uint32_t at = act_addr(act_row, t >> 5, t & 31);
    sts_u(at, pack_bf16(r[0], r[1]));
    sts_u(at + 8, pack_bf16(r[2], r[3]));
}

template <int N>
DEVINL void gather_add(const uint32_t* p, uint32_t tag, uint32_t (&xp)[2], const unsigned* cnt, unsigned expected, int lane) {
    uint4 v[N];
    unsigned n = 0;
    uint32_t bad;
    do {
#pragma unroll
        for (int i = 0; i < N; i++) v[i] = ld_gpu_2b64(p + i * 512);
        bad = 0u;
#pragma unroll
        for (int i = 0; i < N; i++) bad |= (v[i].x ^ tag) | (v[i].z ^ tag);
        if (cnt == nullptr) { if ((bad & 3u) == 0u) break; }
        else {
            if (!__any_sync(0xffffffffu, (bad & 3u) != 0u)) break;
            if (n == 0) hint_wait(cnt, expected, lane);
        }
    } while (++n < SPIN_LIMIT);
    float s0 = 0.f, s1 = 0.f, s2 = 0.f, s3 = 0.f;
#pragma unroll
    for (int i = 0; i < N; i++) { s0 += asf(v[i].x); s1 += asf(v[i].y); s2 += asf(v[i].z); s3 += asf(v[i].w); }
    const uint32_t a0 = pack_bf16(s0, s1), a1 = pack_bf16(s2, s3);
    xp[0] = pack_bf16(bf_lo(xp[0]) + bf_lo(a0), bf_hi(xp[0]) + bf_hi(a0));
    xp[1] = pack_bf16(bf_lo(xp[1]) + bf_lo(a1), bf_hi(xp[1]) + bf_hi(a1));
}
DEVINL void gather_add2(const uint32_t* pa, uint32_t taga, uint32_t (&xa)[2], const uint32_t* pb, uint32_t tagb, uint32_t (&xb)[2],
                        const unsigned* cnt, unsigned expected, int lane) {
    uint4 v[8], u[8];
    unsigned n = 0;
    uint32_t bad;
    do {
#pragma unroll
        for (int i = 0; i < 8; i++) v[i] = ld_gpu_2b64(pa + i * 512);
#pragma unroll
        for (int i = 0; i < 8; i++) u[i] = ld_gpu_2b64(pb + i * 512);
        bad = 0u;
#pragma unroll
        for (int i = 0; i < 8; i++) bad |= ((v[i].x ^ taga) | (v[i].z ^ taga)) | ((u[i].x ^ tagb) | (u[i].z ^ tagb));
        if (!__any_sync(0xffffffffu, (bad & 3u) != 0u)) break;
        if (n == 0) hint_wait(cnt, expected, lane);
    } while (++n < SPIN_LIMIT);
    float s0 = 0.f, s1 = 0.f, s2 = 0.f, s3 = 0.f, t0 = 0.f, t1 = 0.f, t2 = 0.f, t3 = 0.f;
#pragma unroll
    for (int i = 0; i < 8; i++) {
        s0 += asf(v[i].x); s1 += asf(v[i].y); s2 += asf(v[i].z); s3 += asf(v[i].w);
        t0 += asf(u[i].x); t1 += asf(u[i].y); t2 += asf(u[i].z); t3 += asf(u[i].w);
    }
    const uint32_t a0 = pack_bf16(s0, s1), a1 = pack_bf16(s2, s3), b0 = pack_bf16(t0, t1), b1 = pack_bf16(t2, t3);
    xa[0] = pack_bf16(bf_lo(xa[0]) + bf_lo(a0), bf_hi(xa[0]) + bf_hi(a0));
    xa[1] = pack_bf16(bf_lo(xa[1]) + bf_lo(a1), bf_hi(xa[1]) + bf_hi(a1));
    xb[0] = pack_bf16(bf_lo(xb[0]) + bf_lo(b0), bf_hi(xb[0]) + bf_hi(b0));
    xb[1] = pack_bf16(bf_lo(xb[1]) + bf_lo(b1), bf_hi(xb[1]) + bf_hi(b1));
}

DEVINL void warp_stats(const uint32_t (&xp)[2], float piv, float& s1, float& s2) {
    const float d0 = bf_lo(xp[0]) - piv, d1 = bf_hi(xp[0]) - piv, d2 = bf_lo(xp[1]) - piv, d3 = bf_hi(xp[1]) - piv;
    s1 = (d0 + d1) + (d2 + d3);
    s2 = fmaf(d0, d0, d1 * d1) + fmaf(d2, d2, d3 * d3);
#pragma unroll
    for (int off = 1; off < 32; off <<= 1) {
        s1 += __shfl_xor_sync(0xffffffffu, s1, off);
        s2 += __shfl_xor_sync(0xffffffffu, s2, off);
    }
}
DEVINL void ln_scalars(uint32_t stats, float piv, float& mb, float& rden) {
    const float4 a = lds_f4(stats), b = lds_f4(stats + 16);
    const float dm = ((a.x + a.z) + (b.x + b.z)) * (1.f / 512.f);
    const float q = ((a.y + a.w) + (b.y + b.w)) * (1.f / 512.f);
    const float var = bf16r(fmaxf(fmaf(-dm, dm, q), 0.f));
    mb = bf16r(piv + dm);
    rden = __fdividef(1.f, bf16r(__fsqrt_rn(bf16r(var + 1e-5f))));
}

template <int NMT, int KS>
DEVINL void gemv_a(uint32_t w_addr, uint32_t abuf, uint32_t red, int w, int lane, uint32_t zero) {
    constexpr int ROWB = NMT * 32;
    const int krow = w * KS * 16 + (lane & 7) + ((lane >> 4) << 3);
    const int sw = (NMT == 2) ? ((krow >> 1) & 3) : ((krow >> 2) & 1);
    const uint32_t wb = w_addr + krow * ROWB + ((((lane >> 3) & 1) ^ sw) << 4);
    const uint32_t ab = abuf + w * 2048 + ACT_OFF + (lane & 7) * 8;
    uint32_t a[KS][NMT][4];
    uint2 b[KS];
#pragma unroll
    for (int kk = 0; kk < KS; kk++) {
#pragma unroll
        for (int mt = 0; mt < NMT; mt++) ldsm4t(a[kk][mt][0], a[kk][mt][1], a[kk][mt][2], a[kk][mt][3], (wb ^ (mt * 32)) + kk * 16 * ROWB);
        asm volatile("ld.shared.v2.u32 {%0,%1}, [%2];" : "=r"(b[kk].x), "=r"(b[kk].y) : "r"(ab + kk * 64) : "memory");
    }
    const uint32_t dep = b[KS - 1].y & zero;
    float acc[2][NMT][4];
#pragma unroll
    for (int i = 0; i < 2; i++)
#pragma unroll
        for (int mt = 0; mt < NMT; mt++) { acc[i][mt][0] = acc[i][mt][1] = acc[i][mt][2] = acc[i][mt][3] = 0.f; }
#pragma unroll
    for (int kk = 0; kk < KS; kk++)
#pragma unroll
        for (int mt = 0; mt < NMT; mt++) mma16816(acc[kk & 1][mt], a[kk][mt][0], a[kk][mt][1], a[kk][mt][2], a[kk][mt][3], b[kk].x | dep, b[kk].y);
    if ((lane & 3) == 0) {
#pragma unroll
        for (int mt = 0; mt < NMT; mt++)
            sts_f4(red + w * 2048 + (mt * 8 + (lane >> 2)) * 16, acc[0][mt][0] + acc[1][mt][0], acc[0][mt][1] + acc[1][mt][1],
                   acc[0][mt][2] + acc[1][mt][2], acc[0][mt][3] + acc[1][mt][3]);
    }
}
DEVINL void red_sum2(uint32_t scratch, int l, int n, float& v0, float& v1) {
    const int m = (2 * l) & 15, mt = l >> 3;
    const uint32_t a = scratch + (mt * 8 + (m & 7)) * 16 + ((m >> 3) * 2 + n) * 4;
    v0 = (lds_f(a) + lds_f(a + 2048)) + (lds_f(a + 4096) + lds_f(a + 6144));
    v1 = (lds_f(a + 16) + lds_f(a + 2064)) + (lds_f(a + 4112) + lds_f(a + 6160));
}

DEVINL int q_frag_index(int s, int m) {
    const int head = s >> 2, d = 32 * (s & 3) + m;
    const int ks = d >> 4, dd = d & 15;
    const int c = (dd & 7) >> 1, e = (dd & 1) + 2 * (dd >> 3);
    return ((head * 4 + c) * 8 + ks) * 4 + e;
}

DEVINL void chain(bool has_mid, bool has_fin, bool first, int set, int w, int lane, int cta, uint32_t sbase, uint32_t tag_mid, uint32_t tag_fin,
                  const __nv_bfloat16* __restrict__ x, int it, unsigned epoch, uint32_t zero) {
    unsigned* cnt = &g_cnt[set][0][0];
    const unsigned use5 = epoch * 5u + it + 1u;
    const int t = w * 32 + lane;
    const int g = cta >> 4, s = cta & 15;
    const int kq = cta >> 5, nt = cta & 31;
    const uint32_t scratch = sbase + RING_OFF + set * 65536 + 3 * 16384;
    const uint32_t at = act_addr(scratch, w, lane);
    const uint32_t cs = sbase + MISC_OFF + set * MISC_PER_SET + CS_OFF;
    const uint32_t stats = sbase + MISC_OFF + set * MISC_PER_SET + ST_OFF;
    const uint32_t xk = sbase + MISC_OFF + set * MISC_PER_SET + XK_OFF;
    const bool ron = (w < 2) && (w ? has_fin : has_mid);
    const uint32_t tag_w = w ? tag_fin : tag_mid;
    uint32_t xm[2] = {0u, 0u}, xf[2];
    float v0, v1, mb, rden;

    if (first) {
        set_bar(set);
        sts_u(at + 8192, 0x3f803f80u); sts_u(at + 8192 + 8, 0x3f803f80u);
        __syncwarp();
        gemv_a<2, 8>(sbase + WQ_OFF, scratch + 8192, scratch, w, lane, zero);
        set_bar(set);
        if (w == 0 && lane < 16) { red_sum2(scratch, lane, 0, v0, v1); sts_f2(cs + lane * 8, v0, v1); }
        set_bar(set);
        gemv_a<1, 8>(sbase + W1_OFF, scratch + 8192, scratch, w, lane, zero);
        set_bar(set);
        if (w == 0 && lane < 8) { red_sum2(scratch, lane, 0, v0, v1); sts_f2(cs + 128 + lane * 8, v0, v1); }
    }
#pragma unroll 1
    for (int rr = 1; rr >= 0; rr--)
        if (rr ? has_fin : has_mid) {
            if (!SPEC_H && (rr == 0 || !has_mid)) hint_wait(cnt + (rr * 8 + g) * 32, (epoch * 4u + it + 1u - rr) * 64u - (64u * EARLY_H >> 8), lane);
            gather_o(&g_E1[set][rr][g][0][0], &g_E1ml[set][rr][g][0][0], rr ? tag_fin : tag_mid, w, lane, scratch + rr * 32,
                     cnt + (rr * 8 + g) * 32, (epoch * 4u + it + 1u - rr) * 64u - (64u * EARLY_H >> 8));
        }
    set_bar(set);
    gemv_a<2, 8>(sbase + WO_OFF, scratch, scratch, w, lane, zero);
    set_bar(set);
    if (w < 2) {
        if (ron && lane < 16) {
            red_sum2(scratch, lane, w, v0, v1);
            st_gpu_b64(&g_E2[set][w][g][32 * s + 2 * lane], tagged(v0, tag_w), __float_as_uint(v1));
        }
        hint_add(cnt + 16 * 32, lane);
    }
    float pivm = 0.f;
    if (has_mid) {
        const uint2 x0 = __ldg(reinterpret_cast<const uint2*>(x + (2 * it + set) * 512) + t);
        pivm = __bfloat162float(__ldg(x + (2 * it + set) * 512));
        xm[0] = x0.x; xm[1] = x0.y;
    }
    xf[0] = lds32(xk + t * 8); xf[1] = lds32(xk + t * 8 + 4);
    const float pivf = bf_lo(lds32(xk));
    const float piv_w = w ? pivf : pivm;
    if (!SPEC_H) hint_wait(cnt + 16 * 32, use5 * 256u - (256u * EARLY_H >> 8), lane);
    gather_add2(&g_E2[set][has_mid ? 0 : 1][0][4 * t], has_mid ? tag_mid : tag_fin, xm,
                &g_E2[set][has_fin ? 1 : 0][0][4 * t], has_fin ? tag_fin : tag_mid, xf,
                cnt + 16 * 32, use5 * 256u - (256u * EARLY_H >> 8), lane);
    sts_u(at + 8192, xm[0]); sts_u(at + 8192 + 8, xm[1]);
    sts_u(at + 8192 + 32, xf[0]); sts_u(at + 8192 + 40, xf[1]);
    if (cta < 112) {
        __syncwarp();
        gemv_a<1, 8>(sbase + W1_OFF, scratch + 8192, scratch + 8192, w, lane, zero);
        float a1, a2, b1, b2;
        warp_stats(xm, pivm, a1, a2);
        warp_stats(xf, pivf, b1, b2);
        if (lane == 0) { sts_f2(stats + w * 8, a1, a2); sts_f2(stats + 32 + w * 8, b1, b2); }
        set_bar(set);
        if (w < 2) {
            if (ron && lane < 8) {
                red_sum2(scratch + 8192, lane, w, v0, v1);
                ln_scalars(stats + w * 32, piv_w, mb, rden);
                const float2 cv = lds_f2(cs + 128 + lane * 8);
                const uint32_t h01 = pack_bf16((v0 - mb * cv.x) * rden, (v1 - mb * cv.y) * rden);
                const float h0 = bf_lo(h01), h1 = bf_hi(h01);
                st_gpu_b64(&g_E3[set][w][16 * cta + 2 * lane], tag_w, pack_bf16(__fdividef(h0, 1.f + __expf(-h0)), __fdividef(h1, 1.f + __expf(-h1))));
            }
            hint_add(cnt + (17 + ((cta * 2341) >> 16)) * 32, lane);
        }
    }
    {
        const int l28 = lane < 28 ? lane : 27;
        const uint32_t* p0 = &g_E3[set][has_mid ? 0 : 1][448 * kq + 112 * w + 4 * l28];
        const uint32_t* p1 = &g_E3[set][has_fin ? 1 : 0][448 * kq + 112 * w + 4 * l28];
        const uint32_t t0 = has_mid ? tag_mid : tag_fin, t1 = has_fin ? tag_fin : tag_mid;
        uint4 v, u;
        unsigned n = 0;
        if (!SPEC_L) hint_wait(cnt + (17 + kq) * 32, use5 * 56u - (56u * EARLY_L >> 8), lane);
        do {
            v = ld_gpu_2b64(p0);
            u = ld_gpu_2b64(p1);
            if (!__any_sync(0xffffffffu, (((v.x ^ t0) | (v.z ^ t0)) | ((u.x ^ t1) | (u.z ^ t1))) != 0u)) break;
            if (n == 0) hint_wait(cnt + (17 + kq) * 32, use5 * 56u - (56u * EARLY_L >> 8), lane);
        } while (++n < SPIN_LIMIT);
        if (lane < 28) {
            sts_u(at, v.y); sts_u(at + 8, v.w);
            sts_u(at + 32, u.y); sts_u(at + 40, u.w);
        }
    }
    if (cta >= 112) set_bar(set); else __syncwarp();
    gemv_a<1, 7>(sbase + W2_OFF, scratch, scratch, w, lane, zero);
    set_bar(set);
    if (w < 2) {
        if (ron && lane < 8) {
            red_sum2(scratch, lane, w, v0, v1);
            st_gpu_b64(&g_E4[set][w][kq][16 * nt + 2 * lane], tagged(v0, tag_w), __float_as_uint(v1));
        }
        hint_add(cnt + 21 * 32, lane);
    }
    if (has_mid) {
        if (!SPEC_L) hint_wait(cnt + 21 * 32, use5 * 256u - (256u * EARLY_L >> 8), lane);
        gather_add<4>(&g_E4[set][0][0][4 * t], tag_mid, xm, cnt + 21 * 32, use5 * 256u - (256u * EARLY_L >> 8), lane);
        sts_u(at + 8192, xm[0]); sts_u(at + 8192 + 8, xm[1]);
        __syncwarp();
        gemv_a<2, 8>(sbase + WQ_OFF, scratch + 8192, scratch + 8192, w, lane, zero);
        float a1, a2;
        warp_stats(xm, pivm, a1, a2);
        if (lane == 0) sts_f2(stats + w * 8, a1, a2);
        set_bar(set);
        if (w == 0) {
            if (lane < 16) {
                red_sum2(scratch + 8192, lane, 0, v0, v1);
                ln_scalars(stats, pivm, mb, rden);
                const float2 cv = lds_f2(cs + lane * 8);
                st_gpu_v2(&g_Q2[set][g][q_frag_index(s, 2 * lane)], tagged(bf16r((v0 - mb * cv.x) * rden), tag_mid),
                          tagged(bf16r((v1 - mb * cv.y) * rden), tag_mid));
            }
            hint_add(cnt + (24 + g) * 32, lane);
        }
    }
    if (has_fin && t == cta) sts_u2(cs + 192, xf[0], xf[1]);
    sts_u2(xk + t * 8, xm[0], xm[1]);
    __syncwarp();
}

DEVINL void fin_output(int set, int t, int cta, uint32_t sbase, uint32_t tag_fin, __nv_bfloat16* __restrict__ outrow) {
    if (t == cta) {
        const uint32_t a = sbase + MISC_OFF + set * MISC_PER_SET + CS_OFF + 192;
        uint32_t xf[2] = {lds32(a), lds32(a + 4)};
        gather_add<4>(&g_E4[set][1][0][4 * t], tag_fin, xf, nullptr, 0u, 0);
        *reinterpret_cast<uint2*>(outrow + 4 * t) = make_uint2(xf[0], xf[1]);
    }
    __syncwarp();
}

DEVINL void issue_tile(uint32_t sbase, const CUtensorMap* mapK, const CUtensorMap* mapV, int set, int row_b, int n, uint64_t pol) {
    const int slot = n & 3;
    const uint32_t fb = sbase + BAR_OFF + (set * 4 + slot) * 8;
    mbar_expect_tx(fb, 16384);
    const uint32_t dst = sbase + RING_OFF + set * 65536 + slot * 16384;
    const int row = row_b + (2 * (n >> 2) + (n & 1)) * 64;
    tma_3d(dst, (n & 2) ? mapV : mapK, row, 0, fb, pol);
}

__global__ void __launch_bounds__(NTHREADS, 1)
fused_kernel(const __grid_constant__ CUtensorMap mapK, const __grid_constant__ CUtensorMap mapV,
             const __grid_constant__ CUtensorMap mapWq, const __grid_constant__ CUtensorMap mapWo,
             const __grid_constant__ CUtensorMap mapW1, const __grid_constant__ CUtensorMap mapW2,
             const __nv_bfloat16* __restrict__ x, __nv_bfloat16* __restrict__ out, uint32_t zero) {
    extern __shared__ __align__(1024) uint8_t smem_raw[];
    const uint32_t sbase = smem_u32(smem_raw);
    const int tid = threadIdx.x;
    const uint32_t bars = sbase + BAR_OFF;
    const uint32_t bar_wq = bars + 24 * 8, bar_wo = bars + 25 * 8, bar_w = bars + 26 * 8;

    uint32_t xu[8];
    if (tid < 256) {
        const uint4* xp = reinterpret_cast<const uint4*>(x + (tid >> 5) * 512) + (tid & 31) * 2;
        const uint4 u0 = __ldg(xp), u1 = __ldg(xp + 1);
        xu[0] = u0.x; xu[1] = u0.y; xu[2] = u0.z; xu[3] = u0.w; xu[4] = u1.x; xu[5] = u1.y; xu[6] = u1.z; xu[7] = u1.w;
    }
    if (tid == 256) {
        for (int i = 0; i < 8; i++) { mbar_init(bars + i * 8, 1); mbar_init(bars + 64 + i * 8, 4); mbar_init(bars + 128 + i * 8, 4); }
        mbar_init(bar_wq, 1); mbar_init(bar_wo, 1); mbar_init(bar_w, 1);
        asm volatile("fence.mbarrier_init.release.cluster;" ::: "memory");
        asm volatile("fence.proxy.async.shared::cta;" ::: "memory");
    }
    __syncthreads();

    if (tid >= 256) {
        asm volatile("setmaxnreg.dec.sync.aligned.u32 24;");
        const int cta = blockIdx.x;
        const int row_cta = (cta >> 4) * 8192 + (cta & 15) * 512;
        if (tid == 256) {
            mbar_expect_tx(bar_wq, 32768);
            tma_2d(sbase + WQ_OFF, &mapWq, 32 * cta, 0, bar_wq);
            tma_2d(sbase + WQ_OFF + 16384, &mapWq, 32 * cta, 256, bar_wq);
            int landed = -1;
#pragma unroll 1
            for (int i = 0; i < 128; i++) {
                const int b = i >> 4, n = i & 15, set = b & 1, slot = n & 3;
                const uint32_t eb = bars + 64 + (set * 4 + slot) * 8, ep = ((n >> 2) + (set == 1 && slot == 3 ? 0 : 1)) & 1;
                const bool need = (i >= 32 || n >= 4 || i == 19);
                int upto = (i < PRO_A) ? -1 : i - WINDOW;
                const bool blocked = need && n == 0 && !mbar_try(eb, ep);
                if (blocked) upto = i - 1;
#pragma unroll 1
                while (landed < upto) {
                    const int j = ++landed, js = j & 3;
                    mbar_wait1(bars + (((j >> 4) & 1) * 4 + js) * 8, ((j >> 5) * (js == 3 ? 7 : 6) + ((j & 15) >> 2)) & 1);
                }
                if (need) mbar_wait1(eb, ep);
                issue_tile(sbase, &mapK, &mapV, set, row_cta + b * 65536, n, ((n >= 4 && n < 12) || n == 15) ? POL_NORMAL : POL_FIRST);
            }
        } else if (tid == 288) {
            mbar_wait1(bars, 0);
            mbar_wait1(bars, 1);
            mbar_expect_tx(bar_wo, 32768);
            tma_2d(sbase + WO_OFF, &mapWo, 32 * (cta & 15), 512 * (cta >> 4), bar_wo);
            tma_2d(sbase + WO_OFF + 16384, &mapWo, 32 * (cta & 15), 512 * (cta >> 4) + 256, bar_wo);
            mbar_wait1(bar_wo, 0);
            mbar_expect_tx(bar_w, 14336 + (cta < 112 ? 16384 : 0));
            if (cta < 112) {
                tma_2d(sbase + W1_OFF, &mapW1, 16 * cta, 0, bar_w);
                tma_2d(sbase + W1_OFF + 8192, &mapW1, 16 * cta, 256, bar_w);
            }
            tma_2d(sbase + W2_OFF, &mapW2, 16 * (cta & 31), 448 * (cta >> 5), bar_w);
            tma_2d(sbase + W2_OFF + 7168, &mapW2, 16 * (cta & 31), 448 * (cta >> 5) + 224, bar_w);
#pragma unroll 1
            for (int i = 0; i < 72; i++) {
                const int b = i / 9, k = i - b * 9, set = b & 1, it = b >> 1;
                const int n = (k == 0) ? 15 : 3 + k, slot = n & 3;
                const int idx = (slot == 3) ? it * 3 + (k == 0 ? 0 : (n >> 2)) : (n >> 2) - 1;
                mbar_wait1(bars + 128 + (set * 4 + slot) * 8, idx & 1);
                issue_tile(sbase, &mapK, &mapV, set, row_cta + b * 65536, n, POL_FIRST);
            }
        }
    } else {
        asm volatile("setmaxnreg.inc.sync.aligned.u32 240;");
        const unsigned epoch = *reinterpret_cast<volatile unsigned*>(&g_epoch);
        Ctx c;
        {
            const int set = tid >> 7, w = (tid >> 5) & 3, lane = tid & 31;
            const int x7 = lane & 7;
            const uint32_t ringw = sbase + RING_OFF + set * 65536 + w * 2048;
            c.ka = ringw + ((x7 + ((lane >> 3) & 1) * 8) << 7) + (((lane >> 4) ^ x7) << 4);
            c.va = ringw + ((x7 + (lane >> 4) * 8) << 7) + ((((lane >> 3) & 1) ^ x7) << 4);
            c.qa = sbase + MISC_OFF + set * MISC_PER_SET + QS_OFF + (lane & 15) * 16;
            c.full = bars + set * 32;
            c.zero = zero;
            c.lo16 = lane < 16;

            {
                const int cta = blockIdx.x;
                const int row = tid >> 5;
                const uint32_t scratch = sbase + RING_OFF + 65536 + 3 * 16384;
                float v[16];
#pragma unroll
                for (int i = 0; i < 8; i++) { v[2 * i] = bf_lo(xu[i]); v[2 * i + 1] = bf_hi(xu[i]); }
                float sum = 0.f;
#pragma unroll
                for (int i = 0; i < 16; i++) sum += v[i];
#pragma unroll
                for (int off = 1; off < 32; off <<= 1) sum += __shfl_xor_sync(0xffffffffu, sum, off);
                const float mean = sum * (1.f / 512.f);
                float m2 = 0.f;
#pragma unroll
                for (int i = 0; i < 16; i++) { float d = v[i] - mean; m2 = fmaf(d, d, m2); }
#pragma unroll
                for (int off = 1; off < 32; off <<= 1) m2 += __shfl_xor_sync(0xffffffffu, m2, off);
                const float var = bf16r(m2 * (1.f / 512.f));
                const float mb = bf16r(mean);
                const float rden = __fdividef(1.f, bf16r(__fsqrt_rn(bf16r(var + 1e-5f))));
                uint32_t pk[8];
#pragma unroll
                for (int i = 0; i < 8; i++) pk[i] = pack_bf16(bf16r(v[2 * i] - mb) * rden, bf16r(v[2 * i + 1] - mb) * rden);
                const uint32_t a = scratch + (lane >> 3) * 4096 + (lane & 7) * 256 + row * 32;
                sts_u4(a, pk[0], pk[4], pk[1], pk[5]);
                sts_u4(a + 16, pk[2], pk[6], pk[3], pk[7]);
                asm volatile("bar.sync 3, 256;" ::: "memory");
                if (set == 1) {
                    mbar_wait(bar_wq, 0);
                    {
                        const int krow = w * 128 + (lane & 7) + ((lane >> 4) << 3);
                        const uint32_t wb = sbase + WQ_OFF + krow * 64 + ((((lane >> 3) & 1) ^ ((krow >> 1) & 3)) << 4);
                        const uint32_t ab = scratch + w * 4096 + lane * 8;
                        uint32_t af[8][2][4];
                        uint2 bf[8];
#pragma unroll
                        for (int kk = 0; kk < 8; kk++) {
                            ldsm4t(af[kk][0][0], af[kk][0][1], af[kk][0][2], af[kk][0][3], wb + kk * 1024);
                            ldsm4t(af[kk][1][0], af[kk][1][1], af[kk][1][2], af[kk][1][3], (wb ^ 32) + kk * 1024);
                            asm volatile("ld.shared.v2.u32 {%0,%1}, [%2];" : "=r"(bf[kk].x), "=r"(bf[kk].y) : "r"(ab + kk * 256) : "memory");
                        }
                        const uint32_t dep = bf[7].y & zero;
                        float acc[2][2][4];
#pragma unroll
                        for (int i = 0; i < 2; i++)
#pragma unroll
                            for (int mt = 0; mt < 2; mt++) { acc[i][mt][0] = acc[i][mt][1] = acc[i][mt][2] = acc[i][mt][3] = 0.f; }
#pragma unroll
                        for (int kk = 0; kk < 8; kk++)
#pragma unroll
                            for (int mt = 0; mt < 2; mt++) mma16816(acc[kk & 1][mt], af[kk][mt][0], af[kk][mt][1], af[kk][mt][2], af[kk][mt][3], bf[kk].x | dep, bf[kk].y);
#pragma unroll
                        for (int mt = 0; mt < 2; mt++)
                            sts_f4(scratch + w * 4096 + 2304 + (mt * 32 + lane) * 16, acc[0][mt][0] + acc[1][mt][0], acc[0][mt][1] + acc[1][mt][1],
                                   acc[0][mt][2] + acc[1][mt][2], acc[0][mt][3] + acc[1][mt][3]);
                    }
                    set_bar(1);
                    const uint32_t tag_q1 = 1u + epoch % 3u;
#pragma unroll
                    for (int rr = 0; rr < 2; rr++) {
                        const int n = w * 2 + rr;
                        const int mt = lane >> 4, m = lane & 15;
                        const uint32_t a2 = scratch + 2304 + (mt * 32 + (m & 7) * 4 + (n >> 1)) * 16 + ((m >> 3) * 2 + (n & 1)) * 4;
                        float vv = (lds_f(a2) + lds_f(a2 + 4096)) + (lds_f(a2 + 8192) + lds_f(a2 + 12288));
                        st_gpu(&g_Q1[n][cta >> 4][q_frag_index(cta & 15, lane)], tagged(bf16r(vv), tag_q1));
                    }
                    hint_add(&g_cnt[0][32 + (cta >> 4)][0], lane);
                    asm volatile("fence.proxy.async.shared::cta;" ::: "memory");
                    release<3>(c, 64, 0u);
                }
            }
        }

        uint32_t rk0[32], rk1[32], rv0[32], rv1[32];

#pragma unroll 1
        for (int ph = 0; ph < 9; ph++) {
            int tid_l = threadIdx.x, cta = blockIdx.x;
            asm volatile("" : "+r"(tid_l), "+r"(cta));
            const int set = tid_l >> 7, w = (tid_l >> 5) & 3, lane = tid_l & 31;
            const int g = cta >> 4, s = cta & 15;
            const int it = ph >> 1, pass = ph & 1;
            const int b = 2 * it + set;
            const uint32_t tag = 1u + (epoch * 4u + it) % 3u;

            if (ph < 8) {
                float o[8][4];
                Soft st;
                uint32_t p[4];
                float sa[4], sb[4];
                const bool p1 = (pass == 0);
                const uint32_t odd = (uint32_t)it & 1u;
                if (p1) {
                    load_q(&g_Q1[b][g][0], 1u + epoch % 3u, &g_cnt[0][32 + g][0], it == 0 ? (epoch + 1u) * 64u : 0u, set, w, lane, c.qa);
                    if (it >= 2) fin_output(set, tid_l & 127, cta, sbase, 1u + (epoch * 4u + it + 1u) % 3u, out + (b - 4) * 512);
                    mbar_wait(c.full + 0, 0); ld_k<0>(c, rk0); qk(c, rk0, sa); release<0>(c, 64, __float_as_uint(sa[0]));
                    mbar_wait(c.full + 8, 0); ld_k<1>(c, rk1); qk(c, rk1, sb); release<1>(c, 64, __float_as_uint(sb[0]));
                } else {
                    uint32_t f0[32], f1[32];
                    ld_k<0>(c, f0); release<0>(c, 128, dep32(f0));
                    ld_k<1>(c, f1); release<1>(c, 128, dep32(f1));
                    load_q(&g_Q2[set][g][0], tag, &g_cnt[set][24 + g][0], (epoch * 4u + it + 1u) * 16u - (16u * EARLY_L >> 8), set, w, lane, c.qa);
                    if (it < 3 && (tid_l & 127) < 16) pf_l2(&g_Q1[b + 2][g][0] + (tid_l & 15) * 32);
                    qk(c, f0, sa);
                    qk(c, f1, sb);
                }
                st.m0 = st.m1 = -INFINITY; st.l0 = st.l1 = 0.f;
#pragma unroll
                for (int mt = 0; mt < 8; mt++) { o[mt][0] = o[mt][1] = o[mt][2] = o[mt][3] = 0.f; }
                softmax2(sa, sb, st, o, p);
                if (p1) {
                    mbar_wait(c.full + 16, 0); ld_v<2>(c, rv0); pvv(rv0, p[0], p[1], o); release<2>(c, 64, dep_o(o));
                    mbar_wait(c.full + 24, odd); ld_v<3>(c, rv1); pvv(rv1, p[2], p[3], o); release<3>(c, 64, dep_o(o));
                } else {
                    pv_smem<2>(c, p[0], p[1], o); release<2>(c, 128, dep_o(o));
                    mbar_wait(c.full + 24, odd); pv_smem<3>(c, p[2], p[3], o); release<3>(c, 128, dep_o(o));
                    qk(c, rk0, sa);
                    qk(c, rk1, sb);
                    softmax2(sa, sb, st, o, p);
                    pv(rv0, p[0], p[1], o);
                    pv(rv1, p[2], p[3], o);
                }
#pragma unroll 1
                for (int gi = pass; gi < 3; gi++) {
                    const uint32_t par = (uint32_t)(gi + 1) & 1u;
                    const bool rel = !(p1 && gi == 2);
                    const uint32_t which = (p1 || gi == 2) ? 64u : 128u;
                    mbar_wait(c.full + 0, par); qk_smem<0>(c, sa); if (rel) release<0>(c, which, __float_as_uint(sa[0]));
                    mbar_wait(c.full + 8, par); qk_smem<1>(c, sb); if (rel) release<1>(c, which, __float_as_uint(sb[0]));
                    softmax2(sa, sb, st, o, p);
                    mbar_wait(c.full + 16, par); pv_smem<2>(c, p[0], p[1], o); if (rel) release<2>(c, which, dep_o(o));
                    mbar_wait(c.full + 24, par ^ (uint32_t)pass ^ odd); pv_smem<3>(c, p[2], p[3], o); if (gi < 2) release<3>(c, which, dep_o(o));
                }
                finish_pass(o, st, sbase + RING_OFF + set * 65536 + 3 * 16384, set, w, lane, &g_E1[set][pass][g][s][0], &g_E1ml[set][pass][g][s][0], tag, &g_cnt[set][pass * 8 + g][0]);
                if (!p1) {
                    if (ph < 7) {
                        asm volatile("fence.proxy.async.shared::cta;" ::: "memory");
                        release<3>(c, 64, 0u);
                    }
                    if (it == 3) fin_output(set, tid_l & 127, cta, sbase, 1u + (epoch * 4u + it + 2u) % 3u, out + (b - 2) * 512);
                    continue;
                }
            }
            if (ph == 0) { mbar_wait(bar_wq, 0); mbar_wait(bar_wo, 0); mbar_wait(bar_w, 0); }
            chain(ph < 8, ph > 0, ph == 0, set, w, lane, cta, sbase, tag, 1u + (epoch * 4u + it + 2u) % 3u, x, it, epoch, zero);
            if (ph == 8) fin_output(set, tid_l & 127, cta, sbase, 1u + (epoch * 4u + it + 2u) % 3u, out + (b - 2) * 512);
            if (ph < 8) {
                asm volatile("fence.proxy.async.shared::cta;" ::: "memory");
                release<3>(c, 128, 0u);
            }
        }
        asm volatile("bar.sync 3, 256;" ::: "memory");
        if (tid == 0) {
            __threadfence();
            unsigned d = atomicAdd(&g_done, 1u);
            if (d == NCTA - 1) {
                g_done = 0u;
                g_epoch = epoch + 1u;
                __threadfence();
            }
        }
    }
}

typedef CUresult (*EncodeFn)(CUtensorMap*, CUtensorMapDataType, cuuint32_t, void*, const cuuint64_t*, const cuuint64_t*,
                             const cuuint32_t*, const cuuint32_t*, CUtensorMapInterleave, CUtensorMapSwizzle,
                             CUtensorMapL2promotion, CUtensorMapFloatOOBfill);

void make_map_2d(EncodeFn fn, CUtensorMap* m, const void* ptr, uint64_t cols, uint64_t rows, uint32_t bcols, uint32_t brows,
                 CUtensorMapSwizzle sw) {
    cuuint64_t dims[2] = {cols, rows};
    cuuint64_t strides[1] = {cols * 2};
    cuuint32_t box[2] = {bcols, brows};
    cuuint32_t es[2] = {1, 1};
    fn(m, CU_TENSOR_MAP_DATA_TYPE_BFLOAT16, 2, const_cast<void*>(ptr), dims, strides, box, es, CU_TENSOR_MAP_INTERLEAVE_NONE, sw,
       CU_TENSOR_MAP_L2_PROMOTION_NONE, CU_TENSOR_MAP_FLOAT_OOB_FILL_NONE);
}
void make_map_kv(EncodeFn fn, CUtensorMap* m, const void* ptr) {
    cuuint64_t dims[3] = {64, 524288, 2};
    cuuint64_t strides[2] = {256, 128};
    cuuint32_t box[3] = {64, 64, 2};
    cuuint32_t es[3] = {1, 1, 1};
    fn(m, CU_TENSOR_MAP_DATA_TYPE_BFLOAT16, 3, const_cast<void*>(ptr), dims, strides, box, es, CU_TENSOR_MAP_INTERLEAVE_NONE,
       CU_TENSOR_MAP_SWIZZLE_128B, CU_TENSOR_MAP_L2_PROMOTION_NONE, CU_TENSOR_MAP_FLOAT_OOB_FILL_NONE);
}

}

extern "C" void kernel_launch(void* const* d_in, const int* in_sizes, int n_in, void* d_out, int out_size) {
    (void)in_sizes; (void)n_in; (void)out_size;
    static EncodeFn encode = nullptr;
    if (!encode) {
        void* fp = nullptr;
        cudaDriverEntryPointQueryResult qr;
        cudaGetDriverEntryPoint("cuTensorMapEncodeTiled", &fp, cudaEnableDefault, &qr);
        encode = (EncodeFn)fp;
        cudaFuncSetAttribute(fused_kernel, cudaFuncAttributeMaxDynamicSharedMemorySize, SMEM_BYTES);
    }
    CUtensorMap mK, mV, mWq, mWo, mW1, mW2;
    make_map_kv(encode, &mK, d_in[1]);
    make_map_kv(encode, &mV, d_in[2]);
    make_map_2d(encode, &mWq, d_in[3], 4096, 512, 32, 256, CU_TENSOR_MAP_SWIZZLE_64B);
    make_map_2d(encode, &mWo, d_in[4], 512, 4096, 32, 256, CU_TENSOR_MAP_SWIZZLE_64B);
    make_map_2d(encode, &mW1, d_in[6], 1792, 512, 16, 256, CU_TENSOR_MAP_SWIZZLE_32B);
    make_map_2d(encode, &mW2, d_in[7], 512, 1792, 16, 224, CU_TENSOR_MAP_SWIZZLE_32B);
    fused_kernel<<<NCTA, NTHREADS, SMEM_BYTES, cudaStreamPerThread>>>(mK, mV, mWq, mWo, mW1, mW2, (const __nv_bfloat16*)d_in[0],
                                                                    (__nv_bfloat16*)d_out, 0u);
}
```
